```python
import torch

def _softmax(x, axis=-1):
    return torch.softmax(x, dim=axis)

def _gelu(x):
    return torch.nn.functional.gelu(x, approximate='tanh')

def _silu(x):
    return torch.nn.functional.silu(x)

def _sigmoid(x):
    return torch.sigmoid(x)

def _layernorm(x, axis=-1, eps=1e-05):
    m = x.mean(dim=axis, keepdim=True)
    v = x.var(dim=axis, keepdim=True, unbiased=False)
    return (x - m) / torch.sqrt(v + eps)

def _scatter_add(tgt, idx, src, axis=0):
    return tgt.clone().index_add_(axis, idx, src)

def _segment_sum(src, seg, n):
    out = torch.zeros((n,) + src.shape[1:], dtype=src.dtype)
    return out.index_add_(0, seg, src)

def _pad(x, pw):
    flat = tuple((v for pair in reversed(pw) for v in pair))
    return torch.nn.functional.pad(x, flat)
kernel_name = 'adaLN_cond__softmax_full_mha__glu_gated_glu__prompt'

def setup_inputs():

    _w = lambda a: (lambda t: t.to(torch.bfloat16) if t.is_floating_point() else t)(torch.as_tensor(a))

    def _A_setup():
        B, S, D = (1, 2048, 512)
        return {'x': _w((lambda *s: torch.randn(*s, dtype=torch.bfloat16) * 0.05)(B, S, D)), 'wqkv': _w((lambda *s: torch.randn(*s, dtype=torch.bfloat16) * 0.05)(D, 3 * D)), 'wo': _w((lambda *s: torch.randn(*s, dtype=torch.bfloat16) * 0.05)(D, D))}
    _A_in = _A_setup()

    def _B_setup():
        B, S, D, F = (1, 2048, 512, 1792)
        return {'x': _w((lambda *s: torch.randn(*s, dtype=torch.bfloat16) * 0.05)(B, S, D)), 'w_gate': _w((lambda *s: torch.randn(*s, dtype=torch.bfloat16) * 0.05)(D, F)), 'w_up': _w((lambda *s: torch.randn(*s, dtype=torch.bfloat16) * 0.05)(D, F)), 'w_down': _w((lambda *s: torch.randn(*s, dtype=torch.bfloat16) * 0.05)(F, D))}
    _B_in = _B_setup()
    return {'A_x': _A_in['x'], 'A_wqkv': _A_in['wqkv'], 'A_wo': _A_in['wo'], 'B_x': _B_in['x'], 'B_w_gate': _B_in['w_gate'], 'B_w_up': _B_in['w_up'], 'B_w_down': _B_in['w_down'], 'c': _w((lambda *s: torch.randn(*s, dtype=torch.bfloat16) * 0.1)(1, 512) * 8.0), 'w_mod': _w((lambda *s: torch.randn(*s, dtype=torch.bfloat16) * 0.1)(512, 6 * 512) * 512 ** (-0.5) * 8.0)}

def reference(A_x, A_wqkv, A_wo, B_x, B_w_gate, B_w_up, B_w_down, c, w_mod):

    def _A_ref(x, wqkv, wo):
        B, S, D = x.shape
        H = 32
        Dh = D // H
        qkv = (lambda x, *d: x.permute(*d))((x @ wqkv).reshape(B, S, 3, H, Dh), 2, 0, 3, 1, 4)
        q, k, v = (qkv[0], qkv[1], qkv[2])
        scale = Dh ** (-0.5)
        scores = torch.einsum('bhqd,bhkd->bhqk', q, k) * scale
        p = _softmax(scores, axis=-1)
        o = torch.einsum('bhqk,bhkd->bhqd', p, v)
        return (lambda x, *d: x.permute(*d))(o, 0, 2, 1, 3).reshape(B, S, D) @ wo

    def _B_ref(x, w_gate, w_up, w_down):
        g = torch.einsum('bsd,df->bsf', x, w_gate)
        u = torch.einsum('bsd,df->bsf', x, w_up)
        h = _sigmoid(g) * u
        return torch.einsum('bsf,fd->bsd', h, w_down)
    x = A_x
    mod = (_silu(c) @ w_mod).reshape(c.shape[0], 6, 1, -1)
    sa, ca, ga, sb, cb, gb = (mod[:, 0].clone(), mod[:, 1].clone(), mod[:, 2].clone(), mod[:, 3].clone(), mod[:, 4].clone(), mod[:, 5].clone())
    h = _layernorm(x, axis=-1) * (1 + ca) + sa
    x = x + ga * _A_ref(h, A_wqkv, A_wo)
    h = _layernorm(x, axis=-1) * (1 + cb) + sb
    x = x + gb * _B_ref(h, B_w_gate, B_w_up, B_w_down)
    return x
```

```cpp
#include <cuda_runtime.h>
#include <cuda_bf16.h>
#include <cuda.h>
#include <stdint.h>

namespace {

constexpr uint32_t SB = 1024;
constexpr uint32_t SM_W = SB;
constexpr uint32_t SM_G = SM_W + 8 * 16384;
constexpr uint32_t SM_PG = SM_G + 98304, SM_PS = SM_PG + 1024;
constexpr uint32_t SM_GA = SM_PS + 1024, SM_GB = SM_GA + 128, SM_RED = SM_GA, SM_KMAX = SM_GA + 256;
constexpr uint32_t SM_ROLE = SM_KMAX + 16, B_WFULL = SM_ROLE + 8, B_WEMPTY = B_WFULL + 64, B_KFULL = B_WEMPTY + 64, B_KEMPTY = B_KFULL + 48;
constexpr uint32_t B_P2 = B_KEMPTY + 48, B_Q = B_P2 + 8, B_KV = B_Q + 16, B_DONE = B_KV + 8, B_P1 = B_DONE + 8, B_G = B_P1 + 8;
constexpr uint32_t SM_ALLOC = B_G + 8 * 16 - SB;
static_assert(SM_ALLOC <= 232448, "smem");

struct alignas(128) Scratch {
  uint8_t kv[16 * 32 * 8192];
  uint4 o[32 * 32 * 128];
  uint4 x1[32 * 32 * 128];
  uint4 g[32 * 8 * 4 * 14 * 32], part[32 * 8 * 3 * 4 * 128], stat2[32 * 8 * 32];
  uint32_t mod1[8 * 2048], mod2[1024], fmod[32], fkv[16 * 32], epoch[132 * 32];
};
__device__ Scratch g_s;

struct alignas(64) Params {
  const uint8_t *x, *c, *wmod; Scratch* s;
  int never; uint32_t m1;
  uint64_t dw128[5], dw64, dw2, dk, dv, dob;
  uint32_t role[66];
  uint8_t* out; const uint8_t *wqkv, *wo, *wg, *wu, *wd;
  CUtensorMap tm_x, tm_qkv, tm_wo, tm_g64, tm_u64, tm_g32, tm_u32, tm_wd;
};

#define MASKA 0xF736u
#define MASKB 0xF736u
#define TRYPOS 6
#define RELPOS 2
#define CFGS 0x570042u, 0x519090u, 0xCFA447u, 0xBBAF8Du, 0x77A447u, 0x77A447u, 0x6D424Eu, 0xBBD208u

template<int TB, int ACC> __device__ __forceinline__ void wgmma_n24(float (&d)[12], const uint32_t (&a)[4], uint64_t db) {
  if constexpr (ACC != 0)
    asm volatile("wgmma.mma_async.sync.aligned.m64n24k16.f32.bf16.bf16 "
      "{%0, %1, %2, %3, %4, %5, %6, %7, %8, %9, %10, %11}, "
      "{%12, %13, %14, %15}, %16, %18, 1, 1, %17;"
      : "+f"(d[0]), "+f"(d[1]), "+f"(d[2]), "+f"(d[3]), "+f"(d[4]), "+f"(d[5]), "+f"(d[6]), "+f"(d[7]),
        "+f"(d[8]), "+f"(d[9]), "+f"(d[10]), "+f"(d[11])
      : "r"(a[0]), "r"(a[1]), "r"(a[2]), "r"(a[3]), "l"(db), "n"(TB), "n"(ACC & 1));
  else
    asm volatile("wgmma.mma_async.sync.aligned.m64n24k16.f32.bf16.bf16 "
      "{%0, %1, %2, %3, %4, %5, %6, %7, %8, %9, %10, %11}, "
      "{%12, %13, %14, %15}, %16, %18, 1, 1, %17;"
      : "=f"(d[0]), "=f"(d[1]), "=f"(d[2]), "=f"(d[3]), "=f"(d[4]), "=f"(d[5]), "=f"(d[6]), "=f"(d[7]),
        "=f"(d[8]), "=f"(d[9]), "=f"(d[10]), "=f"(d[11])
      : "r"(a[0]), "r"(a[1]), "r"(a[2]), "r"(a[3]), "l"(db), "n"(TB), "n"(ACC & 1));
}
template<int TB, int ACC> __device__ __forceinline__ void wgmma_n64(float (&d)[32], const uint32_t (&a)[4], uint64_t db) {
  if constexpr (ACC != 0)
    asm volatile("wgmma.mma_async.sync.aligned.m64n64k16.f32.bf16.bf16 "
      "{%0, %1, %2, %3, %4, %5, %6, %7, %8, %9, %10, %11, %12, %13, %14, %15, %16, %17, %18, %19, %20, %21, %22, %23, %24, %25, %26, %27, %28, %29, %30, %31}, "
      "{%32, %33, %34, %35}, %36, %38, 1, 1, %37;"
      : "+f"(d[0]), "+f"(d[1]), "+f"(d[2]), "+f"(d[3]), "+f"(d[4]), "+f"(d[5]), "+f"(d[6]), "+f"(d[7]),
        "+f"(d[8]), "+f"(d[9]), "+f"(d[10]), "+f"(d[11]), "+f"(d[12]), "+f"(d[13]), "+f"(d[14]), "+f"(d[15]),
        "+f"(d[16]), "+f"(d[17]), "+f"(d[18]), "+f"(d[19]), "+f"(d[20]), "+f"(d[21]), "+f"(d[22]), "+f"(d[23]),
        "+f"(d[24]), "+f"(d[25]), "+f"(d[26]), "+f"(d[27]), "+f"(d[28]), "+f"(d[29]), "+f"(d[30]), "+f"(d[31])
      : "r"(a[0]), "r"(a[1]), "r"(a[2]), "r"(a[3]), "l"(db), "n"(TB), "n"(ACC & 1));
  else
    asm volatile("wgmma.mma_async.sync.aligned.m64n64k16.f32.bf16.bf16 "
      "{%0, %1, %2, %3, %4, %5, %6, %7, %8, %9, %10, %11, %12, %13, %14, %15, %16, %17, %18, %19, %20, %21, %22, %23, %24, %25, %26, %27, %28, %29, %30, %31}, "
      "{%32, %33, %34, %35}, %36, %38, 1, 1, %37;"
      : "=f"(d[0]), "=f"(d[1]), "=f"(d[2]), "=f"(d[3]), "=f"(d[4]), "=f"(d[5]), "=f"(d[6]), "=f"(d[7]),
        "=f"(d[8]), "=f"(d[9]), "=f"(d[10]), "=f"(d[11]), "=f"(d[12]), "=f"(d[13]), "=f"(d[14]), "=f"(d[15]),
        "=f"(d[16]), "=f"(d[17]), "=f"(d[18]), "=f"(d[19]), "=f"(d[20]), "=f"(d[21]), "=f"(d[22]), "=f"(d[23]),
        "=f"(d[24]), "=f"(d[25]), "=f"(d[26]), "=f"(d[27]), "=f"(d[28]), "=f"(d[29]), "=f"(d[30]), "=f"(d[31])
      : "r"(a[0]), "r"(a[1]), "r"(a[2]), "r"(a[3]), "l"(db), "n"(TB), "n"(ACC & 1));
}
template<int TB, int ACC> __device__ __forceinline__ void wgmma_n128(float (&d)[64], const uint32_t (&a)[4], uint64_t db) {
  if constexpr (ACC != 0)
    asm volatile("wgmma.mma_async.sync.aligned.m64n128k16.f32.bf16.bf16 "
      "{%0, %1, %2, %3, %4, %5, %6, %7, %8, %9, %10, %11, %12, %13, %14, %15, %16, %17, %18, %19, %20, %21, %22, %23, %24, %25, %26, %27, %28, %29, %30, %31, %32, %33, %34, %35, %36, %37, %38, %39, %40, %41, %42, %43, %44, %45, %46, %47, %48, %49, %50, %51, %52, %53, %54, %55, %56, %57, %58, %59, %60, %61, %62, %63}, "
      "{%64, %65, %66, %67}, %68, %70, 1, 1, %69;"
      : "+f"(d[0]), "+f"(d[1]), "+f"(d[2]), "+f"(d[3]), "+f"(d[4]), "+f"(d[5]), "+f"(d[6]), "+f"(d[7]),
        "+f"(d[8]), "+f"(d[9]), "+f"(d[10]), "+f"(d[11]), "+f"(d[12]), "+f"(d[13]), "+f"(d[14]), "+f"(d[15]),
        "+f"(d[16]), "+f"(d[17]), "+f"(d[18]), "+f"(d[19]), "+f"(d[20]), "+f"(d[21]), "+f"(d[22]), "+f"(d[23]),
        "+f"(d[24]), "+f"(d[25]), "+f"(d[26]), "+f"(d[27]), "+f"(d[28]), "+f"(d[29]), "+f"(d[30]), "+f"(d[31]),
        "+f"(d[32]), "+f"(d[33]), "+f"(d[34]), "+f"(d[35]), "+f"(d[36]), "+f"(d[37]), "+f"(d[38]), "+f"(d[39]),
        "+f"(d[40]), "+f"(d[41]), "+f"(d[42]), "+f"(d[43]), "+f"(d[44]), "+f"(d[45]), "+f"(d[46]), "+f"(d[47]),
        "+f"(d[48]), "+f"(d[49]), "+f"(d[50]), "+f"(d[51]), "+f"(d[52]), "+f"(d[53]), "+f"(d[54]), "+f"(d[55]),
        "+f"(d[56]), "+f"(d[57]), "+f"(d[58]), "+f"(d[59]), "+f"(d[60]), "+f"(d[61]), "+f"(d[62]), "+f"(d[63])
      : "r"(a[0]), "r"(a[1]), "r"(a[2]), "r"(a[3]), "l"(db), "n"(TB), "n"(ACC & 1));
  else
    asm volatile("wgmma.mma_async.sync.aligned.m64n128k16.f32.bf16.bf16 "
      "{%0, %1, %2, %3, %4, %5, %6, %7, %8, %9, %10, %11, %12, %13, %14, %15, %16, %17, %18, %19, %20, %21, %22, %23, %24, %25, %26, %27, %28, %29, %30, %31, %32, %33, %34, %35, %36, %37, %38, %39, %40, %41, %42, %43, %44, %45, %46, %47, %48, %49, %50, %51, %52, %53, %54, %55, %56, %57, %58, %59, %60, %61, %62, %63}, "
      "{%64, %65, %66, %67}, %68, %70, 1, 1, %69;"
      : "=f"(d[0]), "=f"(d[1]), "=f"(d[2]), "=f"(d[3]), "=f"(d[4]), "=f"(d[5]), "=f"(d[6]), "=f"(d[7]),
        "=f"(d[8]), "=f"(d[9]), "=f"(d[10]), "=f"(d[11]), "=f"(d[12]), "=f"(d[13]), "=f"(d[14]), "=f"(d[15]),
        "=f"(d[16]), "=f"(d[17]), "=f"(d[18]), "=f"(d[19]), "=f"(d[20]), "=f"(d[21]), "=f"(d[22]), "=f"(d[23]),
        "=f"(d[24]), "=f"(d[25]), "=f"(d[26]), "=f"(d[27]), "=f"(d[28]), "=f"(d[29]), "=f"(d[30]), "=f"(d[31]),
        "=f"(d[32]), "=f"(d[33]), "=f"(d[34]), "=f"(d[35]), "=f"(d[36]), "=f"(d[37]), "=f"(d[38]), "=f"(d[39]),
        "=f"(d[40]), "=f"(d[41]), "=f"(d[42]), "=f"(d[43]), "=f"(d[44]), "=f"(d[45]), "=f"(d[46]), "=f"(d[47]),
        "=f"(d[48]), "=f"(d[49]), "=f"(d[50]), "=f"(d[51]), "=f"(d[52]), "=f"(d[53]), "=f"(d[54]), "=f"(d[55]),
        "=f"(d[56]), "=f"(d[57]), "=f"(d[58]), "=f"(d[59]), "=f"(d[60]), "=f"(d[61]), "=f"(d[62]), "=f"(d[63])
      : "r"(a[0]), "r"(a[1]), "r"(a[2]), "r"(a[3]), "l"(db), "n"(TB), "n"(ACC & 1));
}

__device__ __forceinline__ void wg_fence() { asm volatile("wgmma.fence.sync.aligned;" ::: "memory"); }
__device__ __forceinline__ void wg_commit() { asm volatile("wgmma.commit_group.sync.aligned;" ::: "memory"); }
template<int N> __device__ __forceinline__ void wg_wait() { asm volatile("wgmma.wait_group.sync.aligned %0;" :: "n"(N) : "memory"); }
template<int N> __device__ __forceinline__ void pin(float (&d)[N]) {
  #pragma unroll
  for (int i = 0; i < N; i++) asm volatile("" : "+f"(d[i]) :: "memory");
}
template<int N> __device__ __forceinline__ void pin(uint32_t (&d)[N]) {
  #pragma unroll
  for (int i = 0; i < N; i++) asm volatile("" : "+r"(d[i]) :: "memory");
}
__device__ __forceinline__ void mbar_init(uint32_t b, int c) { asm volatile("mbarrier.init.shared::cta.b64 [%0], %1;" :: "r"(b), "r"(c) : "memory"); }
__device__ __forceinline__ void mbar_expect(uint32_t b, int bytes) { asm volatile("mbarrier.arrive.expect_tx.shared::cta.b64 _, [%0], %1;" :: "r"(b), "r"(bytes) : "memory"); }
__device__ __forceinline__ void mbar_arrive(uint32_t b) { asm volatile("mbarrier.arrive.shared::cta.b64 _, [%0];" :: "r"(b) : "memory"); }
__device__ __forceinline__ void mbar_arrive2_cl(uint32_t b) { asm volatile("mbarrier.arrive.shared::cluster.b64 _, [%0], 2;" :: "r"(b) : "memory"); }
__device__ __forceinline__ void mbar_arrive_cl(uint32_t b) { asm volatile("mbarrier.arrive.shared::cluster.b64 _, [%0];" :: "r"(b) : "memory"); }
__device__ __forceinline__ void mbar_wait(uint32_t b, uint32_t par) {
  asm volatile("{\n.reg .pred p;\nLW:\nmbarrier.try_wait.parity.shared::cta.b64 p, [%0], %1;\n@!p bra LW;\n}\n" :: "r"(b), "r"(par) : "memory");
}
__device__ __forceinline__ void mbar_wait_long(uint32_t b, uint32_t par) {
  asm volatile("{\n.reg .pred p;\nLW:\nmbarrier.try_wait.parity.shared::cta.b64 p, [%0], %1, 100000;\n@!p bra LW;\n}\n" :: "r"(b), "r"(par) : "memory");
}
__device__ __forceinline__ uint32_t mbar_try(uint32_t b, uint32_t par) {
  uint32_t ok;
  asm volatile("{\n.reg .pred p;\nmbarrier.test_wait.parity.shared::cta.b64 p, [%1], %2;\nselp.u32 %0, 1, 0, p;\n}\n" : "=r"(ok) : "r"(b), "r"(par) : "memory");
  return ok;
}
__device__ __forceinline__ void delay_until(uint32_t t0, uint32_t d) { uint32_t t; do { asm volatile("mov.u32 %0, %%clock;" : "=r"(t)); } while (t - t0 < d); }
__device__ __forceinline__ void sched_fence(uint32_t dummy) { asm volatile("{\n.reg .b32 t;\nmov.u32 t, %%clock;\nst.shared.u32 [%0], t;\n}" :: "r"(dummy) : "memory"); }
__device__ __forceinline__ void watchdog(uint32_t t0) { uint32_t t; asm volatile("mov.u32 %0, %%globaltimer_lo;" : "=r"(t)); if (t - t0 > 2000000000u) asm volatile("trap;"); }
__device__ __forceinline__ void mbar_wait_guard(uint32_t b, uint32_t t0) {
  while (true) {
    uint32_t ok;
    asm volatile("{\n.reg .pred p;\nmbarrier.try_wait.parity.shared::cta.b64 p, [%1], 0, 100000;\nselp.u32 %0, 1, 0, p;\n}\n" : "=r"(ok) : "r"(b) : "memory");
    if (ok) break;
    watchdog(t0);
  }
}
__device__ __forceinline__ void cl_arrive_relaxed() { asm volatile("barrier.cluster.arrive.relaxed.aligned;" ::: "memory"); }
__device__ __forceinline__ void cl_wait() { asm volatile("barrier.cluster.wait.acquire.aligned;" ::: "memory"); }
template<int ID, int N> __device__ __forceinline__ void bar_sync() { asm volatile("bar.sync %0, %1;" :: "n"(ID), "n"(N) : "memory"); }
__device__ __forceinline__ void bar_sync_wg(int wg) { asm volatile("bar.sync %0, 128;" :: "r"(5 + wg) : "memory"); }
__device__ __forceinline__ void turn_begin(int wg) { asm volatile("bar.sync %0, 256;" :: "r"(3 + wg) : "memory"); }
__device__ __forceinline__ void turn_end(int wg) { asm volatile("bar.arrive %0, 256;" :: "r"(4 - wg) : "memory"); }
__device__ __forceinline__ void w_load(uint32_t dst, uint32_t bar, int bytes, const CUtensorMap* m, int c0, int c1) {
  if (bytes) asm volatile("{\n.reg .pred p;\nelect.sync _|p, 0xffffffff;\n@p mbarrier.arrive.expect_tx.shared::cta.b64 _, [%0], %2;\n"
                          "@p mbarrier.arrive.expect_tx.shared::cluster.b64 _, [%1], %2;\n}" :: "r"(bar), "r"(bar ^ 0x1000000u), "r"(bytes) : "memory");
  asm volatile("{\n.reg .pred p;\nelect.sync _|p, 0xffffffff;\n"
               "@p cp.async.bulk.tensor.2d.shared::cluster.global.mbarrier::complete_tx::bytes.multicast::cluster [%0], [%1, {%3, %4}], [%2], %5;\n}"
               :: "r"(dst), "l"(m), "r"(bar), "r"(c0), "r"(c1), "h"((uint16_t)3) : "memory");
}
__device__ __forceinline__ void tma3d(uint32_t dst, const CUtensorMap* m, int c1, int c2, uint32_t bar) {
  asm volatile("cp.async.bulk.tensor.3d.shared::cluster.global.mbarrier::complete_tx::bytes [%0], [%1, {%3, %4, %5}], [%2];"
    :: "r"(dst), "l"(m), "r"(bar), "r"(0), "r"(c1), "r"(c2) : "memory");
}
__device__ __forceinline__ void bulk_g2s(uint32_t dst, const void* src, int bytes, uint32_t bar) {
  asm volatile("cp.async.bulk.shared::cluster.global.mbarrier::complete_tx::bytes [%0], [%1], %2, [%3];" :: "r"(dst), "l"(src), "r"(bytes), "r"(bar) : "memory");
}
__device__ __forceinline__ void bulk_s2g(void* dst, uint32_t src, int bytes) {
  asm volatile("cp.async.bulk.global.shared::cta.bulk_group [%0], [%1], %2;" :: "l"(dst), "r"(src), "r"(bytes) : "memory");
}
__device__ __forceinline__ uint32_t tile_off() { uint32_t l; asm volatile("mov.u32 %0, %%laneid;" : "=r"(l)); return ((l & 15) << 7) + (((l >> 4) ^ (l & 7)) << 4); }
__device__ __forceinline__ bool elect() { uint32_t p; asm volatile("{\n.reg .pred p;\nelect.sync _|p, 0xffffffff;\nselp.u32 %0, 1, 0, p;\n}\n" : "=r"(p)); return p; }
__device__ __forceinline__ uint4 ldg_nc4(const void* p) { uint4 v; asm volatile("ld.global.nc.v4.u32 {%0,%1,%2,%3}, [%4];" : "=r"(v.x), "=r"(v.y), "=r"(v.z), "=r"(v.w) : "l"(p)); return v; }
__device__ __forceinline__ uint32_t ldg_nc1(const void* p) { uint32_t v; asm volatile("ld.global.nc.u32 %0, [%1];" : "=r"(v) : "l"(p)); return v; }
__device__ __forceinline__ void ld_wk4(uint32_t (&a)[4], const void* p) { asm volatile("ld.global.v4.u32 {%0,%1,%2,%3}, [%4];" : "=r"(a[0]), "=r"(a[1]), "=r"(a[2]), "=r"(a[3]) : "l"(p) : "memory"); }
__device__ __forceinline__ void ld_rlx4(uint32_t (&a)[4], const void* p) {
  asm volatile("{\n.reg .b128 v;\n.reg .b64 l, h;\nld.relaxed.gpu.global.b128 v, [%4];\nmov.b128 {l, h}, v;\nmov.b64 {%0, %1}, l;\nmov.b64 {%2, %3}, h;\n}"
               : "=r"(a[0]), "=r"(a[1]), "=r"(a[2]), "=r"(a[3]) : "l"(p) : "memory");
}
__device__ __forceinline__ uint32_t ld_rlx1(const void* p) { uint32_t v; asm volatile("ld.relaxed.gpu.global.u32 %0, [%1];" : "=r"(v) : "l"(p) : "memory"); return v; }
__device__ __forceinline__ uint32_t ld_acq1(const void* p) { uint32_t v; asm volatile("ld.acquire.gpu.global.u32 %0, [%1];" : "=r"(v) : "l"(p) : "memory"); return v; }
__device__ __forceinline__ void st_rlx4(void* p, uint32_t a, uint32_t b, uint32_t c, uint32_t d) {
  asm volatile("{\n.reg .b128 v;\n.reg .b64 l, h;\nmov.b64 l, {%1, %2};\nmov.b64 h, {%3, %4};\nmov.b128 v, {l, h};\nst.relaxed.gpu.global.b128 [%0], v;\n}"
               :: "l"(p), "r"(a), "r"(b), "r"(c), "r"(d) : "memory");
}
template<class T> __device__ __forceinline__ T* fix(T* p) { asm volatile("" : "+l"(p)); return p; }
__device__ __forceinline__ void st_tag4(void* p, uint32_t a, uint32_t b, uint32_t c, uint32_t d, uint32_t par) { st_rlx4(p, (a & ~1u) | par, b, c, d); }
__device__ __forceinline__ void st_rlx1(void* p, uint32_t a) { asm volatile("st.relaxed.gpu.global.u32 [%0], %1;" :: "l"(p), "r"(a) : "memory"); }
__device__ __forceinline__ void st_async4(uint32_t a, uint32_t x, uint32_t y, uint32_t z, uint32_t w, uint32_t bar) {
  asm volatile("st.async.weak.shared::cluster.mbarrier::complete_tx::bytes.v4.b32 [%0], {%1,%2,%3,%4}, [%5];" :: "r"(a), "r"(x), "r"(y), "r"(z), "r"(w), "r"(bar) : "memory");
}
__device__ __forceinline__ void ldsm4(uint32_t (&r)[4], uint32_t a) { asm volatile("ldmatrix.sync.aligned.m8n8.x4.shared.b16 {%0,%1,%2,%3}, [%4];" : "=r"(r[0]), "=r"(r[1]), "=r"(r[2]), "=r"(r[3]) : "r"(a) : "memory"); }
__device__ __forceinline__ void ldsm4t(uint32_t (&r)[4], uint32_t a) { asm volatile("ldmatrix.sync.aligned.m8n8.x4.trans.shared.b16 {%0,%1,%2,%3}, [%4];" : "=r"(r[0]), "=r"(r[1]), "=r"(r[2]), "=r"(r[3]) : "r"(a) : "memory"); }
__device__ __forceinline__ void stsm4t(uint32_t a, uint32_t x, uint32_t y, uint32_t z, uint32_t w) { asm volatile("stmatrix.sync.aligned.m8n8.x4.trans.shared.b16 [%0], {%1,%2,%3,%4};" :: "r"(a), "r"(x), "r"(y), "r"(z), "r"(w) : "memory"); }
__device__ __forceinline__ void stsm4(uint32_t a, uint32_t x, uint32_t y, uint32_t z, uint32_t w) { asm volatile("stmatrix.sync.aligned.m8n8.x4.shared.b16 [%0], {%1,%2,%3,%4};" :: "r"(a), "r"(x), "r"(y), "r"(z), "r"(w) : "memory"); }
__device__ __forceinline__ void lds4(uint32_t (&v)[4], uint32_t a) { asm volatile("ld.shared.v4.u32 {%0,%1,%2,%3}, [%4];" : "=r"(v[0]), "=r"(v[1]), "=r"(v[2]), "=r"(v[3]) : "r"(a) : "memory"); }
__device__ __forceinline__ void lds4f(float* v, uint32_t a) { asm volatile("ld.shared.v4.f32 {%0,%1,%2,%3}, [%4];" : "=f"(v[0]), "=f"(v[1]), "=f"(v[2]), "=f"(v[3]) : "r"(a) : "memory"); }
__device__ __forceinline__ float2 lds2f(uint32_t a) { float2 v; asm volatile("ld.shared.v2.f32 {%0,%1}, [%2];" : "=f"(v.x), "=f"(v.y) : "r"(a) : "memory"); return v; }
__device__ __forceinline__ uint32_t lds1(uint32_t a) { uint32_t v; asm volatile("ld.shared.u32 %0, [%1];" : "=r"(v) : "r"(a) : "memory"); return v; }
__device__ __forceinline__ void sts4(uint32_t a, uint32_t x, uint32_t y, uint32_t z, uint32_t w) { asm volatile("st.shared.v4.u32 [%0], {%1,%2,%3,%4};" :: "r"(a), "r"(x), "r"(y), "r"(z), "r"(w) : "memory"); }
__device__ __forceinline__ void sts2(uint32_t a, uint32_t x, uint32_t y) { asm volatile("st.shared.v2.u32 [%0], {%1,%2};" :: "r"(a), "r"(x), "r"(y) : "memory"); }
__device__ __forceinline__ void sts1(uint32_t a, uint32_t x) { asm volatile("st.shared.u32 [%0], %1;" :: "r"(a), "r"(x) : "memory"); }
__device__ __forceinline__ uint32_t pk(float lo, float hi) { uint32_t r; asm("cvt.rn.bf16x2.f32 %0, %1, %2;" : "=r"(r) : "f"(hi), "f"(lo)); return r; }
__device__ __forceinline__ float blo(uint32_t v) { return __uint_as_float(v << 16); }
__device__ __forceinline__ float bhi(uint32_t v) { return __uint_as_float(v & 0xFFFF0000u); }
__device__ __forceinline__ float rbf(float v) { return blo(pk(v, 0.f)); }
__device__ __forceinline__ uint32_t hfma2(uint32_t a, uint32_t b, uint32_t c) { uint32_t r; asm("fma.rn.bf16x2 %0, %1, %2, %3;" : "=r"(r) : "r"(a), "r"(b), "r"(c)); return r; }
__device__ __forceinline__ uint32_t habsmax2(uint32_t a, uint32_t b) { uint32_t r; asm("max.xorsign.abs.bf16x2 %0, %1, %2;" : "=r"(r) : "r"(a), "r"(b)); return r; }
__device__ __forceinline__ uint32_t tagacc(uint32_t x, uint32_t v, uint32_t par) { uint32_t r; asm("lop3.b32 %0, %1, %2, %3, 0xF6;" : "=r"(r) : "r"(x), "r"(v), "r"(par)); return r; }
__device__ __forceinline__ float ex2(float x) { float r; asm("ex2.approx.ftz.f32 %0, %1;" : "=f"(r) : "f"(x)); return r; }
__device__ __forceinline__ float rcp(float x) { float r; asm("rcp.approx.ftz.f32 %0, %1;" : "=f"(r) : "f"(x)); return r; }
__device__ __forceinline__ float rsq(float x) { float r; asm("rsqrt.approx.ftz.f32 %0, %1;" : "=f"(r) : "f"(x)); return r; }
__device__ __forceinline__ float tanhx(float x) { float r; asm("tanh.approx.f32 %0, %1;" : "=f"(r) : "f"(x)); return r; }
__device__ __forceinline__ float shx(float v, int m) { return __shfl_xor_sync(0xffffffffu, v, m); }
__device__ __forceinline__ float silu_bf(uint32_t c16) { const float v = __uint_as_float(c16 << 16); return rbf(v * rcp(1.f + ex2(-1.4426950408889634f * v))); }
template<int N> __device__ __forceinline__ bool stale(const uint32_t (*a)[4], uint32_t par) {
  uint32_t x = 0;
  #pragma unroll
  for (int k = 0; k < N; k++) x = tagacc(x, a[k][0], par);
  return __any_sync(0xffffffffu, x & 1);
}

struct Gather {
  uint32_t buf, buf3, bar, ph, par; const uint8_t* src; int lane;
  template<int H> __device__ __forceinline__ void issue() {
    mbar_expect(bar + 8 * H, 8192);
    if (H == 0) { bulk_g2s(buf3, src, 4096, bar); bulk_g2s(buf, src + 4096, 4096, bar); }
    else bulk_g2s(buf + 4096, src + 8192, 8192, bar + 8);
  }
  __device__ __forceinline__ void start() { if (elect()) { issue<0>(); issue<1>(); } }
  __device__ __forceinline__ void wait(int h) { mbar_wait(bar + 8 * h, (ph >> h) & 1); ph ^= 1u << h; }
  template<int H> __device__ __forceinline__ void half(uint32_t (*d)[4]) {
    #pragma unroll 1
    while (true) {
      wait(H);
      #pragma unroll
      for (int k = 16 * H; k < 16 * H + 16; k++) lds4(d[k & 15], (k < 8 ? buf3 : buf - 4096) + k * 512 + lane * 16);
      if (!stale<16>(d, par)) break;
      if (elect()) issue<H>();
    }
  }
};

__device__ __forceinline__ uint32_t exp2_mufu(float a, float b) { return pk(ex2(a), ex2(b)); }
constexpr float QSCALE = 0.25f * 1.4426950408889634f;
constexpr float EXP_BIAS = 382.41760546875f;
template<bool ALT> __device__ __forceinline__ uint32_t exp2_alu(float ta, float tb, uint32_t m1) {
  uint32_t y, zh;
  asm("prmt.b32 %0, %1, %2, 0x6521;" : "=r"(y) : "r"(__float_as_uint(ta)), "r"(__float_as_uint(tb)));
  asm("lop3.b32 %0, %1, 0x007F007F, 0xBF00BF00, 0xEA;" : "=r"(zh) : "r"(y));
  if (ALT) return (hfma2(zh, zh, 0x3F003F00u) * m1 + zh) * m1 + y;
  return hfma2(y, zh, y & 0x7F807F80u);
}
template<int U> __device__ __forceinline__ void softmax_tile(float (&s)[32], uint32_t (&p)[4][4], uint32_t m1) {
  constexpr uint32_t cfgs[8] = {CFGS}, CFG = cfgs[U], MASK = (U & 1) ? MASKB : MASKA;
  constexpr bool FIRST = U < 2;
  #pragma unroll
  for (int n = 0; n < 16; n++) {
    const int i = (n * ((CFG >> 16) & 15) + (CFG >> 20)) & 15;
    if ((MASK >> i) & 1) {
      if (FIRST) { s[2 * i] += EXP_BIAS; s[2 * i + 1] += EXP_BIAS; }
      p[i >> 2][i & 3] = ((CFG >> i) & 1) ? exp2_alu<true>(s[2 * i], s[2 * i + 1], m1) : exp2_alu<false>(s[2 * i], s[2 * i + 1], m1);
    } else p[i >> 2][i & 3] = exp2_mufu(s[2 * i], s[2 * i + 1]);
  }
  if (FIRST) pin(s);
  #pragma unroll
  for (int i = 0; i < 4; i++) pin(p[i]);
}
__device__ __forceinline__ void pv_tile(const uint32_t (&p)[4][4], float (&o)[12], uint64_t d) {
  #pragma unroll
  for (int k = 0; k < 4; k++) wgmma_n24<1, true>(o, p[k], d + k * 16);
}
template<int U> __device__ __forceinline__ void attn_step(float (&sn)[32], const uint32_t (&q)[4], uint64_t dk, const uint32_t (&pp)[4][4], float (&o)[12], uint64_t dv,
                                                                        float (&s)[32], uint32_t (&p)[4][4], uint32_t m1) {
  wg_fence();
  wgmma_n64<0, (U == 0 || U == 7) ? 2 : 1>(sn, q, dk);
  wg_commit();
  pv_tile(pp, o, dv);
  wg_commit();
  softmax_tile<U>(s, p, m1);
  wg_wait<1>();
  pin(sn);
}
__device__ __forceinline__ void mma16816(float (&d)[4], const uint32_t (&a)[4], uint32_t b0, uint32_t b1) {
  asm("mma.sync.aligned.m16n8k16.row.col.f32.bf16.bf16.f32 {%0,%1,%2,%3}, {%4,%5,%6,%7}, {%8,%9}, {%0,%1,%2,%3};"
    : "+f"(d[0]), "+f"(d[1]), "+f"(d[2]), "+f"(d[3]) : "r"(a[0]), "r"(a[1]), "r"(a[2]), "r"(a[3]), "r"(b0), "r"(b1));
}
__device__ __forceinline__ void mma1688(float (&d)[4], uint32_t a0, uint32_t a1, uint32_t b) {
  asm("mma.sync.aligned.m16n8k8.row.col.f32.bf16.bf16.f32 {%0,%1,%2,%3}, {%4,%5}, {%6}, {%0,%1,%2,%3};" : "+f"(d[0]), "+f"(d[1]), "+f"(d[2]), "+f"(d[3]) : "r"(a0), "r"(a1), "r"(b));
}
__device__ __forceinline__ uint32_t movt(uint32_t v) { uint32_t r; asm("movmatrix.sync.aligned.m8n8.trans.b16 %0, %1;" : "=r"(r) : "r"(v)); return r; }
__device__ __forceinline__ void put_cores(uint4* p, uint32_t scr, uint32_t m0, uint32_t m1, uint32_t m2, uint32_t m3, uint32_t par) {
  stsm4(scr, m0, m1, m2, m3);
  __syncwarp();
  uint32_t v[4]; lds4(v, scr);
  const uint32_t w = (scr >> 7) & 3;
  #pragma unroll
  for (int i = 0; i < 4; i++) { const uint32_t m = w == i; v[i] = (v[i] & ~m) | (par & m); }
  st_rlx4(p, v[0], v[1], v[2], v[3]);
}
__device__ __noinline__ void attn_safe(const uint8_t* kvp, uint32_t qa, uint4* op, uint32_t scr, uint32_t par) {
  for (int blk = 0; blk < 4; blk++) {
    uint32_t q[4]; lds4(q, qa + blk * 2048);
    float o0[4] = {0, 0, 0, 0}, o1[4] = {0, 0, 0, 0}, m0 = -INFINITY, m1 = -INFINITY, l0 = 0.f, l1 = 0.f;
    #pragma unroll 1
    for (int kv = 0; kv < 2048; kv += 16) {
      const uint8_t* b = kvp + (kv >> 7) * 262144 + (kv & 127) * 16;
      float s0[4] = {0, 0, 0, 0}, s1[4] = {0, 0, 0, 0};
      mma16816(s0, q, ld_rlx1(b), ld_rlx1(b + 2048));
      mma16816(s1, q, ld_rlx1(b + 128), ld_rlx1(b + 2048 + 128));
      #pragma unroll
      for (int i = 0; i < 4; i++) { s0[i] *= QSCALE; s1[i] *= QSCALE; }
      const uint32_t v00 = movt(ld_rlx1(b + 4096)), v01 = movt(ld_rlx1(b + 4096 + 128)), v10 = movt(ld_rlx1(b + 6144)), v11 = movt(ld_rlx1(b + 6144 + 128));
      float t0 = fmaxf(fmaxf(s0[0], s0[1]), fmaxf(s1[0], s1[1])), t1 = fmaxf(fmaxf(s0[2], s0[3]), fmaxf(s1[2], s1[3]));
      t0 = fmaxf(t0, shx(t0, 1)); t0 = fmaxf(t0, shx(t0, 2)); t1 = fmaxf(t1, shx(t1, 1)); t1 = fmaxf(t1, shx(t1, 2));
      const float n0 = fmaxf(m0, t0), n1 = fmaxf(m1, t1), c0 = ex2(m0 - n0), c1 = ex2(m1 - n1);
      m0 = n0; m1 = n1;
      const uint32_t p[4] = {pk(ex2(s0[0] - n0), ex2(s0[1] - n0)), pk(ex2(s0[2] - n1), ex2(s0[3] - n1)), pk(ex2(s1[0] - n0), ex2(s1[1] - n0)), pk(ex2(s1[2] - n1), ex2(s1[3] - n1))};
      l0 = l0 * c0 + blo(p[0]) + bhi(p[0]) + blo(p[2]) + bhi(p[2]);
      l1 = l1 * c1 + blo(p[1]) + bhi(p[1]) + blo(p[3]) + bhi(p[3]);
      o0[0] *= c0; o0[1] *= c0; o0[2] *= c1; o0[3] *= c1; o1[0] *= c0; o1[1] *= c0; o1[2] *= c1; o1[3] *= c1;
      mma16816(o0, p, v00, v01);
      mma16816(o1, p, v10, v11);
    }
    l0 += shx(l0, 1); l0 += shx(l0, 2); l1 += shx(l1, 1); l1 += shx(l1, 2);
    const float i0 = rcp(l0), i1 = rcp(l1);
    put_cores(op + blk * 4096, scr + blk * 512, pk(o0[0] * i0, o0[1] * i0), pk(o1[0] * i0, o1[1] * i0), pk(o0[2] * i1, o0[3] * i1), pk(o1[2] * i1, o1[3] * i1), par);
  }
}

template<bool ACC> __device__ __forceinline__ void mm(float (&d)[32], const uint32_t (&a)[4], uint64_t b) { wgmma_n64<1, ACC>(d, a, b); }
template<bool ACC> __device__ __forceinline__ void mm(float (&d)[64], const uint32_t (&a)[4], uint64_t b) { wgmma_n128<1, ACC>(d, a, b); }
struct Pass { uint64_t d; uint32_t me, ph; int wg; bool rel, hand; };
template<int SL> __device__ __forceinline__ void w_release(const Pass& W) { if (W.rel) mbar_arrive_cl(((SL & 1) << 24) + B_WEMPTY + 8 * SL); }
template<int S0, int PM, int NS, int KS, int KSTEP, int N, int NREL = NS, bool ACC0 = false, int J = 0, int NA>
__device__ __forceinline__ void gemm_slots(const Pass& W, float (&acc)[N / 2], const uint32_t (&a)[NA][4]) {
  if constexpr (J < NS) {
    constexpr int SL = (S0 + J) & 7;
    mbar_wait(W.me + B_WFULL + 8 * SL, W.ph ^ ((PM >> J) & 1));
    wg_fence();
    mm<(ACC0 || J > 0)>(acc, a[J * KS], W.d + SL * 1024);
    #pragma unroll
    for (int k = 1; k < KS; k++) mm<true>(acc, a[J * KS + k], W.d + (SL * 1024 + k * KSTEP));
    wg_commit();
    if constexpr (J > 0 && J <= NREL) { wg_wait<1>(); w_release<(S0 + J - 1) & 7>(W); }
    gemm_slots<S0, PM, NS, KS, KSTEP, N, NREL, ACC0, J + 1>(W, acc, a);
  } else if (W.hand) turn_end(W.wg);
}
template<int SL, int N> __device__ __forceinline__ void gemm_finish(const Pass& W, float (&acc)[N]) { wg_wait<0>(); if constexpr (SL >= 0) w_release<SL>(W); pin(acc); }

template<int S0, int K0, bool ACC0> __device__ __forceinline__ void gemm_pairs(const Pass& W, float (&acc)[64], const uint32_t (&a)[28][4]) {
  #pragma unroll
  for (int j = 0; j < 2; j++) {
    mbar_wait(W.me + B_WFULL + 8 * (S0 + 2 * j), W.ph ^ j); mbar_wait(W.me + B_WFULL + 8 * (S0 + 2 * j + 1), W.ph ^ j);
    wg_fence();
    if (j == 0) mm<ACC0>(acc, a[K0], W.d + S0 * 1024);
    #pragma unroll
    for (int k = (j == 0); k < 7; k++) mm<true>(acc, a[K0 + 7 * j + k], W.d + ((S0 + 2 * j) * 1024 + k * 128));
    wg_commit();
  }
  turn_end(W.wg);
  wg_wait<1>(); w_release<S0>(W); w_release<S0 + 1>(W);
}
__device__ __forceinline__ void modulate(uint32_t (*d)[4], const uint32_t (*x)[4], uint32_t sp, uint32_t rs0, uint32_t nm0, uint32_t rs1, uint32_t nm1) {
  uint32_t gg[4], ss[4];
  lds4(gg, sp + SM_PG); lds4(ss, sp + SM_PS);
  #pragma unroll
  for (int i = 0; i < 4; i++) {
    d[i >> 1][(i & 1) * 2] = hfma2(hfma2(x[i >> 1][(i & 1) * 2], rs0, nm0), gg[i], ss[i]);
    d[i >> 1][(i & 1) * 2 + 1] = hfma2(hfma2(x[i >> 1][(i & 1) * 2 + 1], rs1, nm1), gg[i], ss[i]);
  }
}
__device__ __forceinline__ uint32_t max_norm2(const float* d, int lane, float seed = 0.f) {
  float n2[8];
  #pragma unroll
  for (int i = 0; i < 8; i++) { const float* e = d + (i >> 1) * 8 + (i & 1) * 2; n2[i] = fmaf(e[5], e[5], fmaf(e[4], e[4], fmaf(e[1], e[1], fmaf(e[0], e[0], seed)))); }
  const bool h1 = lane & 2, h0 = lane & 1;
  #pragma unroll
  for (int i = 0; i < 4; i++) n2[i] = (h1 ? n2[i + 4] : n2[i]) + shx(h1 ? n2[i] : n2[i + 4], 2);
  #pragma unroll
  for (int i = 0; i < 2; i++) n2[i] = (h0 ? n2[i + 2] : n2[i]) + shx(h0 ? n2[i] : n2[i + 2], 1);
  return max(__float_as_uint(n2[0]), __float_as_uint(n2[1]));
}
template<int N> __device__ __forceinline__ void anchor(uint32_t (&a)[N][4], bool never, uint32_t addr) {
  if (__builtin_expect(never, 0)) {
    #pragma unroll
    for (int k = 0; k < N; k++) sts4(addr + 16 * k, a[k][0], a[k][1], a[k][2], a[k][3]);
  }
  #pragma unroll
  for (int k = 0; k < N; k++) pin(a[k]);
}
__device__ __forceinline__ void put_o(uint4* p, uint32_t scr, float (&o)[12], uint32_t par) {
  pin(o);
  const float i0 = rcp(o[8]), i1 = rcp(o[10]);
  put_cores(p, scr, pk(o[0] * i0, o[1] * i0), pk(o[4] * i0, o[5] * i0), pk(o[2] * i1, o[3] * i1), pk(o[6] * i1, o[7] * i1), par);
}
template<int NP> __device__ __forceinline__ void glu(const float (&acc)[4 * NP], uint32_t* gout) {
  #pragma unroll
  for (int i = 0; i < NP; i++) {
    const float u0 = acc[2 * NP + 2 * i], u1 = acc[2 * NP + 2 * i + 1];
    gout[i] = pk(fmaf(u0, tanhx(acc[2 * i]), u0), fmaf(u1, tanhx(acc[2 * i + 1]), u1));
  }
}

__global__ void __launch_bounds__(384, 1) fused_block_kernel(const __grid_constant__ Params P) {
  extern __shared__ __align__(1024) uint8_t smem_raw[];
  const int warp = __shfl_sync(0xffffffffu, threadIdx.x >> 5, 0);
  uint32_t clk0; asm volatile("mov.u32 %0, %%clock;" : "=r"(clk0));
#define ROLE_VARS(TID) \
  uint32_t tid, sm_, rho; asm volatile("mov.u32 %0, " TID ";\nmov.u32 %1, %%smid;\nmov.u32 %2, %%cluster_ctarank;" : "=r"(tid), "=r"(sm_), "=r"(rho)); \
  const int lane = tid & 31, role = P.role[__shfl_sync(0xffffffffu, sm_, 0) >> 1], pr = role >> 3, r = role & 7, c = 2 * pr + rho; \
  const uint32_t me = rho << 24;                       \
  (void)lane; (void)c; (void)r;

  uint32_t sm0; asm volatile("mov.u32 %0, %%smid;" : "=r"(sm0));
  if ((sm0 >> 2) == 30) {
    ROLE_VARS("%%tid.x")
    const uint32_t epoch = ld_rlx1(P.s->epoch + blockIdx.x * 32) + 1, par = epoch & 1;
    const int hid = (role - 64) * 2 + rho;
    __nanosleep(2500);
    if (warp >= 8) {
      const int i = tid - 256;
      if (i < 92) {
        const uint8_t* src = i < 8 ? P.wo + (hid * 8 + i) * 16384 : i < 36 ? P.wg + (hid * 28 + i - 8) * 16384 : i < 64 ? P.wu + (hid * 28 + i - 36) * 16384 : P.wd + (hid * 28 + i - 64) * 16384;
        asm volatile("cp.async.bulk.prefetch.L2.global [%0], 16384;" :: "l"(src) : "memory");
      }
    } else {
      { const uint32_t cv = ldg_nc1(P.c + tid * 4); sts2(me + SB + tid * 8, __float_as_uint(silu_bf(cv & 0xFFFFu)), __float_as_uint(silu_bf(cv >> 16))); }
      bar_sync<1, 256>();
      const int cg = tid & 63, rg = tid >> 6;
      const uint8_t* w = P.wmod + (size_t)rg * 128 * 6144 + (1024 + hid * 512 + cg * 8) * 2;
      float a[8] = {0, 0, 0, 0, 0, 0, 0, 0};
      #pragma unroll 1
      for (int k0 = 0; k0 < 128; k0 += 8) {
        uint4 v[8];
        #pragma unroll
        for (int k = 0; k < 8; k++) v[k] = ldg_nc4(w + (k0 + k) * 6144);
        #pragma unroll
        for (int k = 0; k < 8; k++) {
          const float s = __uint_as_float(lds1(me + SB + (rg * 128 + k0 + k) * 4));
          a[0] += s * blo(v[k].x); a[1] += s * bhi(v[k].x); a[2] += s * blo(v[k].y); a[3] += s * bhi(v[k].y);
          a[4] += s * blo(v[k].z); a[5] += s * bhi(v[k].z); a[6] += s * blo(v[k].w); a[7] += s * bhi(v[k].w);
        }
      }
      sts4(me + SB + 4096 + rg * 2048 + cg * 32, __float_as_uint(a[0]), __float_as_uint(a[1]), __float_as_uint(a[2]), __float_as_uint(a[3]));
      sts4(me + SB + 4096 + rg * 2048 + cg * 32 + 16, __float_as_uint(a[4]), __float_as_uint(a[5]), __float_as_uint(a[6]), __float_as_uint(a[7]));
      bar_sync<1, 256>();
      const float2 s0 = lds2f(me + SB + 4096 + tid * 8), s1 = lds2f(me + SB + 6144 + tid * 8), s2 = lds2f(me + SB + 8192 + tid * 8), s3 = lds2f(me + SB + 10240 + tid * 8);
      float v0 = rbf((s0.x + s1.x) + (s2.x + s3.x)), v1 = rbf((s0.y + s1.y) + (s2.y + s3.y));
      if (hid == 2) { v0 += 1.f; v1 += 1.f; }
      if (hid == 1 || hid == 2) P.s->mod2[(2 - hid) * 256 + (tid >> 4) * 16 + (tid & 3) * 4 + ((tid >> 2) & 3)] = pk(0.5f * v0, 0.5f * v1);
      else P.s->mod2[512 + (tid >> 5) * 64 + (hid ? 32 : 0) + (tid & 3) * 8 + ((tid >> 2) & 7)] = pk(v0, v1);
      bar_sync<1, 256>();
      if (tid == 0) asm volatile("st.release.gpu.global.u32 [%0], %1;" :: "l"(P.s->fmod + hid), "r"(par) : "memory");
      if (tid == 0) P.s->epoch[blockIdx.x * 32] = epoch;
    }
    return;
  }
  if (warp >= 8) {
    uint32_t epoch, par, t0;
   {
    ROLE_VARS("%%tid.x")
    asm volatile("mov.u32 %0, %%globaltimer_lo;" : "=r"(t0));
    {
      if (elect()) asm volatile("cp.async.bulk.prefetch.L2.global [%0], 2048;" :: "l"(P.wmod + ((role * 2 + rho) * 4 + warp - 8) * 6144) : "memory");
      __syncwarp();
      cl_arrive_relaxed();
      asm volatile("setmaxnreg.dec.sync.aligned.u32 40;");
      const int tau = tid - 256, row = rho * 256 + (tau >> 1) * 4;
      uint4 w[4];
      #pragma unroll
      for (int i = 0; i < 4; i++) w[i] = ldg_nc4(P.wmod + (size_t)(row + i) * 6144 + role * 32 + (tau & 1) * 16);
      uint32_t c0, c1; asm volatile("ld.global.nc.v2.u32 {%0,%1}, [%2];" : "=r"(c0), "=r"(c1) : "l"(P.c + row * 2));
      epoch = ld_rlx1(P.s->epoch + blockIdx.x * 32);
      uint32_t* mout = P.s->mod1 + (tau >> 4) * 2048 + rho * 1024 + role * 16 + (tau & 15);
      const float sc[4] = {silu_bf(c0 & 0xFFFFu), silu_bf(c0 >> 16), silu_bf(c1 & 0xFFFFu), silu_bf(c1 >> 16)};
      float v[8] = {0, 0, 0, 0, 0, 0, 0, 0};
      #pragma unroll
      for (int i = 0; i < 4; i++) {
        v[0] += sc[i] * blo(w[i].x); v[1] += sc[i] * bhi(w[i].x); v[2] += sc[i] * blo(w[i].y); v[3] += sc[i] * bhi(w[i].y);
        v[4] += sc[i] * blo(w[i].z); v[5] += sc[i] * bhi(w[i].z); v[6] += sc[i] * blo(w[i].w); v[7] += sc[i] * bhi(w[i].w);
      }
      pin(v);
      const bool h4 = lane & 16, h3 = lane & 8, h2 = lane & 4;
      #pragma unroll
      for (int i = 0; i < 4; i++) v[i] = (h4 ? v[i + 4] : v[i]) + shx(h4 ? v[i] : v[i + 4], 16);
      #pragma unroll
      for (int i = 0; i < 2; i++) v[i] = (h3 ? v[i + 2] : v[i]) + shx(h3 ? v[i] : v[i + 2], 8);
      v[0] = (h2 ? v[1] : v[0]) + shx(h2 ? v[0] : v[1], 4);
      v[0] += shx(v[0], 2);
      if (!(lane & 2)) sts1(me + SM_RED + (((lane & 1) * 8 + (lane >> 2)) * 4 + warp - 8) * 4, __float_as_uint(v[0]));
      bar_sync<2, 128>();
      epoch = __shfl_sync(0xffffffffu, epoch, 0) + 1; par = epoch & 1;
      float u[4]; lds4f(u, me + SM_RED + (tau & 15) * 16);
      st_rlx1(mout, (__float_as_uint((u[0] + u[1]) + (u[2] + u[3])) & ~1u) | par);
    }
    cl_wait();
    if (warp == 8) {
      const uint32_t fb = me + B_WFULL + 8 * rho, dst = me + SM_W + rho * 16384;
      w_load(dst, fb, 16384, &P.tm_qkv, 512 + r * 64, rho * 64); w_load(dst + 8192, fb, 0, &P.tm_qkv, 1024 + r * 64, rho * 64);
      if (elect()) asm volatile("cp.async.bulk.prefetch.L2.global [%0], 12288;" :: "l"(P.wqkv + (c * 8 + r) * 12288) : "memory");
    }
    __syncwarp();
    {
      const uint32_t* mp = P.s->mod1 + pr * 2048 + (warp - 8) * 256 + lane * 4;
      uint32_t v[4][4];
      delay_until(clk0, 3800);
      ld_wk4(v[0], mp); ld_wk4(v[1], mp + 1024); ld_wk4(v[2], mp + 128); ld_wk4(v[3], mp + 1152);
      while (true) {
        bool any = false;
        #pragma unroll
        for (int k = 0; k < 4; k++)
          if (tagacc(tagacc(tagacc(v[k][0] ^ par, v[k][1], par), v[k][2], par), v[k][3], par) & 1) { ld_rlx4(v[k], mp + (k & 1) * 1024 + (k >> 1) * 128); any = true; }
        if (!__any_sync(0xffffffffu, any)) break;
        watchdog(t0);
      }
      #pragma unroll
      for (int k = 0; k < 2; k++) {
        float x[4];
        #pragma unroll
        for (int e = 0; e < 4; e++) { x[e] = __uint_as_float(v[2 * k][e]) + __uint_as_float(v[2 * k + 1][e]); if (warp & 2) x[e] = 1.f + rbf(x[e]); }
        const uint32_t pa = me + SM_PS - (warp & 2) * 512 + ((warp & 1) * 2 + k) * 256 + (lane >> 3) * 64 + ((lane >> 1) & 3) * 4 + (lane & 1) * 32;
        sts1(pa, pk(x[0], x[1])); sts1(pa + 16, pk(x[2], x[3]));
      }
      mbar_arrive(me + B_P1);
    }
   }
    asm volatile("setmaxnreg.dec.sync.aligned.u32 24;");
    if (warp == 8) {
      ROLE_VARS("%%laneid")
      {
        uint32_t eph = 0;
        auto load = [&](uint32_t slot, bool wait, int bytes, const CUtensorMap* m0, int n0, int k0, const CUtensorMap* m1, int n1, int k1) {
          const uint32_t dst = me + SM_W + slot * 16384, fb = me + B_WFULL + 8 * slot;
          if (wait) { mbar_wait_long(fb + 64, (eph >> slot) & 1); eph ^= 1u << slot; }
          w_load(dst, fb, bytes, m0, n0, k0);
          if (m1) w_load(dst + 8192, fb, 0, m1, n1, k1);
        };
        #pragma unroll 1
        for (int s = rho + 2; s < 8; s += 2) load(s, s >= 6, 16384, &P.tm_qkv, 512 + r * 64, s * 64, &P.tm_qkv, 1024 + r * 64, s * 64);
        #pragma unroll 1
        for (int s = rho; s < 4; s += 2) load(s, true, 16384, &P.tm_qkv, r * 64, s * 128, &P.tm_qkv, r * 64, s * 128 + 64);
        mbar_wait_long(me + B_KFULL + 16, 0);
        #pragma unroll 1
        for (int s = rho; s < 4; s += 2) load(s + 2, true, 16384, &P.tm_wo, r * 64, s * 128, nullptr, 0, 0);
        #pragma unroll 1
        for (int i = rho; i < 24; i += 2) load(i & 7, true, 16384, &P.tm_g64, r * 224 + (i >> 3) * 64, (i & 7) * 64, &P.tm_u64, r * 224 + (i >> 3) * 64, (i & 7) * 64);
        #pragma unroll 1
        for (int s = rho; s < 4; s += 2) load(s, true, 16384, &P.tm_g32, r * 224 + 192, s * 128, &P.tm_u32, r * 224 + 192, s * 128);
        #pragma unroll 1
        for (int i = 0; i < 8; i++) {
          const int n = i < 4 ? 2 + 2 * rho : i < 6 ? 6 : 0, k = i < 4 ? (r ^ (i >> 1)) * 224 + (i & 1) * 112 : (r ^ (i & 1)) * 224 + rho * 112;
          load((2 * i + 4 + rho) & 7, true, 14336, &P.tm_wd, ((r + n) & 7) * 64, k, nullptr, 0, 0);
        }
      }
    } else if (warp < 11) {
      ROLE_VARS("%%laneid")
      const int w = warp - 9;
      const uint32_t kb = me + SM_G + w * 49152, fb0 = me + B_KFULL + w * 24;
      if (lane == 0) { mbar_arrive(fb0); mbar_expect(fb0 + 8, 8192); }
      uint32_t kmax;
      mbar_wait_long(me + B_KV, 0);
      if (elect()) {
        uint8_t* dst = P.s->kv + (c * 32 + 4 * r + w) * 8192;
        bulk_s2g(dst + rho * 16384, kb, 8192); bulk_s2g(dst + (rho ^ 1) * 16384, kb + 20480, 8192);
        mbar_wait_long(me + B_Q + 8 * w, 0);
        asm volatile("cp.async.bulk.shared::cluster.shared::cta.mbarrier::complete_tx::bytes [%0], [%1], 8192, [%2];"
                     :: "r"((kb + 10240) ^ 0x1000000u), "r"(kb + 20480), "r"((fb0 + 8) ^ 0x1000000u) : "memory");
        asm volatile("cp.async.bulk.commit_group;\ncp.async.bulk.wait_group 0;\nfence.proxy.async.global;\nfence.acq_rel.gpu;" ::: "memory");
        mbar_wait(fb0 + 8, 0);
        st_rlx1(P.s->fkv + (r * 2 + w) * 32 + c, (lds1(me + SM_KMAX) & ~1u) | par);
      }
      __syncwarp();
      const uint8_t* src = P.s->kv + (4 * r + 2 * rho + w) * 8192;
      #pragma unroll 1
      for (int pass = 0; pass < 2; pass++) {
        const uint32_t need = pass ? 0xFFFFu : (1u << ((2 * pr + 2) & 15)) | (1u << (c ^ 1));
        while (true) { kmax = ld_acq1(P.s->fkv + (r * 2 + w) * 32 + (lane & 15)); if (!(__ballot_sync(0xffffffffu, (kmax ^ par) & 1) & need)) break; __nanosleep(64); }
        asm volatile("fence.proxy.async.global;" ::: "memory");
        if (!pass && elect()) { mbar_expect(fb0 + 16, 8192); bulk_g2s(kb + 20480, src + ((2 * pr + 2) & 15) * 262144, 8192, fb0 + 16); }
      }
      sts1(me + SM_KMAX + 4 + 4 * w, __reduce_max_sync(0xffffffffu, kmax));
      uint32_t st = 0, ph = 0;
      #pragma unroll 1
      for (int j = 2 * pr + 3; j < 2 * pr + 16; j++) {
        mbar_wait_long(fb0 + 48 + 8 * st, ph);
        if (elect()) { mbar_expect(fb0 + 8 * st, 8192); bulk_g2s(kb + st * 10240, src + (j & 15) * 262144, 8192, fb0 + 8 * st); }
        if (++st == 3) { st = 0; ph ^= 1; }
      }
    } else {
      ROLE_VARS("%%laneid")
      if ((uint32_t)__cvta_generic_to_shared(smem_raw) != me + SB) t0 -= 3000000000u;
      watchdog(t0);
      #pragma unroll 1
      for (int w = 0; w < 2; w++) {
        const int wq = lane >> 3, rw = (2 * c + w) * 4 + wq;
        st_rlx4(P.s->o + (pr * 4 + ((lane >> 1) & 3)) * 4096 + (4 * r + 2 * rho + w) * 128 + wq * 32 + 30 + (lane & 1), 0, 0, 0, par ^ 1);
        st_tag4(P.s->stat2 + (rw * 8 + r) * 8 + (lane & 7), 0, 0, 0, 0, par ^ 1);
        st_tag4(P.s->x1 + rw * 1024 + (4 * r + 3) * 32 + 24 + (lane & 7), 0, 0, 0, 0, par ^ 1);
      }
      mbar_wait_guard(me + B_KFULL + 16, t0);
      { uint32_t o; asm volatile("ld.shared::cluster.u32 %0, [%1];" : "=r"(o) : "r"((me ^ 0x1000000u) + SM_ROLE) : "memory"); if (o != role) t0 -= 3000000000u; watchdog(t0); }
      {
        const uint32_t z = me + SM_G + 38912;
        #pragma unroll 4
        for (int i = 0; i < 16; i++) sts1(z + i * 512 + lane * 16, par ^ 1);
        asm volatile("fence.proxy.async.shared::cta;" ::: "memory");
        __syncwarp();
        if (elect()) {
          #pragma unroll 1
          for (int i = 0; i < 8; i++) {
            bulk_s2g(P.s->g + (((2 * c + (i >> 2)) * 8 + r) * 4 + (i & 3)) * 448 + 384, z, 1024);
            if (i < 2) bulk_s2g(P.s->part + (2 * c + i) * 12288 + (((r + 6) & 7) * 3 + 2) * 512, z, 8192);
          }
          asm volatile("cp.async.bulk.commit_group;\ncp.async.bulk.wait_group 0;" ::: "memory");
        }
        __syncwarp();
      }
      while (__any_sync(0xffffffffu, ld_acq1(P.s->fmod + (lane & 3)) != par)) { watchdog(t0); __nanosleep(1000); }
      asm volatile("fence.proxy.async.global;" ::: "memory");
      if (elect()) {
        mbar_expect(me + B_P2, 2304 + 64);
        bulk_g2s(me + SM_PG, P.s->mod2, 2048, me + B_P2); bulk_g2s(me + SM_GA, P.s->mod2 + 512 + r * 64, 256, me + B_P2);
        #pragma unroll 1
        for (int q = 0; q < 8; q++) { mbar_expect(me + B_G + q * 16, 4096); tma3d(me + SM_W + 6 * 16384 + q * 4096, &P.tm_x, c * 128 + q * 16, r & 6, me + B_G + q * 16); }
      }
      if (lane == 0) P.s->epoch[blockIdx.x * 32] = epoch;
      mbar_wait_guard(me + B_DONE, t0);
    }
    __syncwarp();
    cl_arrive_relaxed(); cl_wait();
  } else {
    ROLE_VARS("%%tid.x")
    const int wg = warp >> 2, wq = warp & 3, tau = tid & 127, g = lane >> 2, t = lane & 3;
    const int rb = 2 * c + wg, xrow = rb * 64 + wq * 16;
    const uint32_t kvb = me + SM_G + wg * 49152;
    const bool l0 = lane == 0;
    Gather G; G.buf = kvb + wq * 12288; G.buf3 = me + SM_W + 6 * 16384 + warp * 4096; G.bar = me + B_G + warp * 16; G.ph = 0; G.lane = lane;
    uint32_t par;
    uint32_t a[32][4];
    {
      if (elect()) {
        mbar_init(G.bar, 1); mbar_init(G.bar + 8, 1);
        mbar_init(me + B_WFULL + 8 * warp, 1); mbar_init(me + B_WEMPTY + 8 * warp, 16);
        if (warp < 6) { mbar_init(me + B_KFULL + 8 * warp, 1); mbar_init(me + B_KEMPTY + 8 * warp, 4); }
        else {
          const uint32_t o = (warp - 6) * 8;
          mbar_init(me + B_Q + o, 9); mbar_expect(me + B_Q + o, 4096); mbar_init(me + B_KV + o, 8);
          mbar_init(me + (o ? B_P1 : B_P2), o ? 128 : 1); sts1(me + SM_KMAX + (o ? 12 : 0), 0); sts1(me + SM_ROLE, role);
        }
        asm volatile("fence.mbarrier_init.release.cluster;" ::: "memory");
      }
      __syncwarp();
      cl_arrive_relaxed();
      if (elect()) {
        delay_until(clk0, wg ? 2700 : 800);
        asm volatile("cp.async.bulk.prefetch.L2.global [%0], 2048;" :: "l"(P.x + (xrow + 2 * r) * 1024) : "memory");
        mbar_expect(G.bar, 8192); mbar_expect(G.bar + 8, 8192);
        tma3d(G.buf, &P.tm_x, xrow, 0, G.bar); tma3d(G.buf + 4096, &P.tm_x, xrow, 2, G.bar);
        tma3d(G.buf + 8192, &P.tm_x, xrow, 4, G.bar + 8); tma3d(G.buf3, &P.tm_x, xrow, 6, G.bar + 8);
        if (warp == 7) asm volatile("prefetch.tensormap [%0];" :: "l"(&P.tm_qkv) : "memory");
      }
      __syncwarp();
      asm volatile("setmaxnreg.inc.sync.aligned.u32 232;");
      par = ~__shfl_sync(0xffffffffu, ld_rlx1(P.s->epoch + blockIdx.x * 32), 0) & 1;
      cl_wait();
      const uint32_t xo = tile_off();
      float sq0[2][4] = {}, sq1[2][4] = {}, sm[2][4] = {};
      #pragma unroll
      for (int h = 0; h < 2; h++) {
        G.wait(h);
        #pragma unroll
        for (int k = 16 * h; k < 16 * h + 16; k++) ldsm4(a[k], (xo ^ ((k & 3) << 5)) + (k < 24 ? G.buf + (k >> 2) * 2048 : G.buf3 + ((k >> 2) & 1) * 2048));
        #pragma unroll
        for (int k = 16 * h; k < 16 * h + 16; k++) {
          mma1688(sq0[0], a[k][0], a[k][1], a[k][0]); mma1688(sq1[0], a[k][0], a[k][1], a[k][1]);
          mma1688(sq0[1], a[k][2], a[k][3], a[k][2]); mma1688(sq1[1], a[k][2], a[k][3], a[k][3]);
          mma16816(sm[k & 1], a[k], 0x3F803F80u, 0x3F803F80u);
        }
      }
      const int src = (lane & 28) | (g >> 1);
      const float q0 = __shfl_sync(0xffffffffu, (g & 1) ? sq0[0][1] + sq0[1][1] : sq0[0][0] + sq0[1][0], src);
      const float q1 = __shfl_sync(0xffffffffu, (g & 1) ? sq1[0][3] + sq1[1][3] : sq1[0][2] + sq1[1][2], src);
      const float m0 = (sm[0][0] + sm[1][0]) * (1.f / 512.f), m1 = (sm[0][2] + sm[1][2]) * (1.f / 512.f);
      const float r0 = rsq(fmaxf(q0 * (1.f / 512.f) - m0 * m0, 0.f) + 1e-5f), r1 = rsq(fmaxf(q1 * (1.f / 512.f) - m1 * m1, 0.f) + 1e-5f);
      const uint32_t rs0 = pk(r0, r0), rs1 = pk(r1, r1), nm0 = pk(-m0 * blo(rs0), -m0 * blo(rs0)), nm1 = pk(-m1 * blo(rs1), -m1 * blo(rs1));
      if (l0) mbar_arrive2_cl(wg * 0x1000008 + B_WEMPTY + 48);
      #pragma unroll
      for (int k = 0; k < 32; k++) { a[k][0] = hfma2(a[k][0], rs0, nm0); a[k][1] = hfma2(a[k][1], rs1, nm1); a[k][2] = hfma2(a[k][2], rs0, nm0); a[k][3] = hfma2(a[k][3], rs1, nm1); pin(a[k]); }
      mbar_wait(me + B_P1, 0);
      asm volatile("setmaxnreg.inc.sync.aligned.u32 240;");
      if (wg) bar_sync<7, 256>();
      #pragma unroll
      for (int m = 0; m < 16; m++) {
        uint32_t gg[4], ss[4];
        lds4(gg, me + SM_PG + t * 16 + m * 64); lds4(ss, me + SM_PS + t * 16 + m * 64);
        #pragma unroll
        for (int i = 0; i < 8; i++) a[2 * m + (i >> 2)][i & 3] = hfma2(a[2 * m + (i >> 2)][i & 3], gg[i >> 1], ss[i >> 1]);
      }
      anchor(a, P.never, me + SM_W);
    }
    if (!wg) asm volatile("bar.arrive 7, 256;" ::: "memory");
    G.par = par;
    {
      float acc[64];
      const Pass W{P.dw128[0], me, 0, wg, l0, true};
      if (wg) turn_begin(wg);
      gemm_slots<0, 0, 8, 4, 128, 128, 6>(W, acc, a);
      #pragma unroll
      for (int i = 0; i < 3; i++) sts4(kvb + 8192 + i * 10240 + tau * 16, 0x3F803F80u, 0x3F803F80u, 0x3F803F80u, 0x3F803F80u);
      gemm_finish<-1>(W, acc);
      const uint32_t ka = me + SM_G + (wg * 64 + wq * 16 + (lane & 15)) * 16 + (lane >> 4) * 2048;
      uint32_t vm = 0;
      #pragma unroll
      for (int j = 0; j < 8; j++) {
        const int h = j & 3; const uint32_t other = (h >> 1) ^ rho;
        const float* d = &acc[8 * j];
        const uint32_t u0 = pk(d[0], d[1]), u1 = pk(d[2], d[3]), u2 = pk(d[4], d[5]), u3 = pk(d[6], d[7]);
        stsm4(ka + other * 20480 + (j >> 2) * 4096 + (h & 1) * 49152, u0, u1, u2, u3);
        if (j >= 4) vm = habsmax2(habsmax2(vm, habsmax2(u0, u1)), habsmax2(u2, u3));
      }
      const uint32_t kn = max_norm2(acc, lane);
      const uint32_t km = __reduce_max_sync(0xffffffffu, fmaxf(fabsf(blo(vm)), fabsf(bhi(vm))) > 1e7f ? 0x7F800000u : kn);
      asm volatile("fence.proxy.async.shared::cta;" ::: "memory");
      __syncwarp();
      if (l0) { asm volatile("red.shared.max.u32 [%0], %1;" :: "r"(me + SM_KMAX), "r"(km) : "memory"); mbar_arrive(me + B_KV); }
    }
    {
      float acc[32];
      const Pass W{P.dw128[1], me, 1, wg, l0, true};
      turn_begin(wg);
      gemm_slots<0, 0, 4, 8, 128, 64>(W, acc, a);
      gemm_finish<3>(W, acc);
      const uint32_t d = me + SM_G + 30720 + (rb & 3) * 2048 + tau * 16;
      #pragma unroll
      for (int h = 0; h < 4; h++) {
        const uint32_t u0 = pk(acc[8 * h], acc[8 * h + 1]), u1 = pk(acc[8 * h + 2], acc[8 * h + 3]), u2 = pk(acc[8 * h + 4], acc[8 * h + 5]), u3 = pk(acc[8 * h + 6], acc[8 * h + 7]);
        if ((h >> 1) == rho) sts4(d + (h & 1) * 49152, u0, u1, u2, u3);
        else st_async4((d ^ 0x1000000u) + (h & 1) * 49152, u0, u1, u2, u3, (me ^ 0x1000000u) + B_Q + (h & 1) * 8);
      }
      __syncwarp();
      if (lane < 2) mbar_arrive(me + B_Q + lane * 8);
      const uint32_t qm = __reduce_max_sync(0xffffffffu, max_norm2(acc, lane, __uint_as_float(lds1(me + SM_KMAX) & 1)));
      if (lane < 2) asm volatile("red.async.relaxed.cluster.shared::cluster.mbarrier::complete_tx::bytes.max.u32 [%0], %1, [%2];"
                                 :: "r"((lane << 24) + SM_KMAX + 12), "r"(qm), "r"((lane << 24) + B_P2) : "memory");
    }
    const uint32_t xo_ = tile_off();
    {
      uint32_t q[4][4];
      float o[4][12], sa[32], sc[32];
      uint32_t p0[4][4], p1[4][4], p2[4][4], p3[4][4];
      #pragma unroll
      for (int b = 0; b < 4; b++) {
        #pragma unroll
        for (int i = 0; i < 12; i++) o[b][i] = 0.f;
        pin(o[b]);
        #pragma unroll
        for (int i = 0; i < 4; i++) p3[b][i] = 0u;
        pin(p3[b]);
      }
      mbar_wait(me + B_KV, 0);
      mbar_wait(me + B_Q + wg * 8, 0);
      {
        float e[8];
        #pragma unroll
        for (int b = 0; b < 4; b++) {
          uint32_t f[4]; lds4(f, kvb + 30720 + ((b >> 1) + (b & 1) * 2) * 2048 + tau * 16);
          #pragma unroll
          for (int i = 0; i < 4; i++) {
            q[b][i] = b ? pk(fmaf(blo(f[i]), QSCALE, -e[2 * i]), fmaf(bhi(f[i]), QSCALE, -e[2 * i + 1])) : pk(blo(f[i]) * QSCALE, bhi(f[i]) * QSCALE);
            e[2 * i] = b ? e[2 * i] + blo(q[b][i]) : blo(q[b][i]); e[2 * i + 1] = b ? e[2 * i + 1] + bhi(q[b][i]) : bhi(q[b][i]);
          }
          pin(q[b]);
        }
      }
      const uint32_t fb0 = me + B_KFULL + wg * 24;
      const uint64_t dk = P.dk + wg * 3072, dv = P.dv + wg * 3072;
      wg_fence();
      wgmma_n64<0, 0>(sa, q[0], dk); wgmma_n64<0, 0>(sc, q[0], dk + 64);
      wg_commit();
      wg_wait<0>();
      pin(sa); pin(sc);
      const int head = 4 * r + 2 * rho + wg;
      uint64_t kb = dk, vb = dv;
      uint32_t fb = fb0, pm = 0x1C71Cu * 2 + 0x80000000u;
      uint64_t step = 0;
      #pragma unroll 1
      while (true) {
        const uint64_t vp = vb; vb += step;
        const uint32_t eb = (fb == fb0 ? fb0 + 24 : fb) + 40;
        const bool wrap = fb == fb0 + 16, rel = (int)pm >= 0 && l0;
        step = wrap ? (uint64_t)-1280 : 640;
        attn_step<0>(sc, q[0], kb + 64, p3, o[3], vp + 64, sa, p0, P.m1);
        fb = wrap ? fb0 : fb + 8;
        pm >>= 1;
        uint32_t ok;
#define HOOK(u) if (RELPOS == u && rel) mbar_arrive(eb); if (TRYPOS == u) ok = mbar_try(fb, pm & 1);
        attn_step<1>(sa, q[1], kb, p0, o[0], vb, sc, p1, P.m1);
        HOOK(2)
        attn_step<2>(sc, q[1], kb + 64, p1, o[0], vb + 64, sa, p2, P.m1);
        HOOK(3)
        attn_step<3>(sa, q[2], kb, p2, o[1], vb, sc, p3, P.m1);
        HOOK(4)
        attn_step<4>(sc, q[2], kb + 64, p3, o[1], vb + 64, sa, p0, P.m1);
        HOOK(5)
        attn_step<5>(sa, q[3], kb, p0, o[2], vb, sc, p1, P.m1);
        HOOK(6)
        attn_step<6>(sc, q[3], kb + 64, p1, o[2], vb + 64, sa, p2, P.m1);
        if (!ok) { if (pm < 0x10000u) break; mbar_wait(fb, pm & 1); }
        kb += step;
        attn_step<7>(sa, q[0], kb, p2, o[3], vb, sc, p3, P.m1);
      }
      uint4* op = P.s->o + pr * 16384 + head * 128 + tau;
      const uint32_t scr = kvb + 38912 + wq * 2048 + lane * 16;
      wg_fence();
      pv_tile(p2, o[3], dv);
      wg_commit();
      mbar_wait(me + B_P2, 0);
      const bool unsafe = !(__uint_as_float(lds1(me + SM_KMAX + 12)) * __uint_as_float(lds1(me + SM_KMAX + 4 + 4 * wg)) <= 8100.f / (QSCALE * QSCALE));
      if (!unsafe) { put_o(op, scr, o[0], par); put_o(op + 8192, scr + 512, o[1], par); }
      softmax_tile<7>(sc, p3, P.m1);
      wg_fence();
      pv_tile(p3, o[3], dv + 64);
      wg_commit();
      wg_wait<2>();
      if (!unsafe) put_o(op + 4096, scr + 1024, o[2], par);
      wg_wait<0>();
      if (unsafe) attn_safe(P.s->kv + head * 8192 + lane * 4, kvb + 30720 + tau * 16, op, scr, par);
      else put_o(op + 12288, scr + 1536, o[3], par);
    }
    {
      uint32_t xv[4][4];
      const uint32_t xo = xo_;
      G.wait(0);
      #pragma unroll
      for (int k = 0; k < 4; k++) ldsm4(xv[k], G.buf3 + (r & 1) * 2048 + (xo ^ (k << 5)));
      #pragma unroll
      for (int j = 0; j < 4; j++) mbar_wait(me + B_WFULL + 16 + 8 * j, j >> 1);
      const uint32_t wa = me + SM_W + 2 * 16384 + ((lane & 7) + (lane >> 4) * 8) * 128 + (((2 * wq + ((lane >> 3) & 1)) ^ (lane & 7)) << 4);
      #pragma unroll
      for (int k = 0; k < 4; k++) ldsm4t(a[k], wa + k * 2048);
      const uint8_t* osrc = (const uint8_t*)(P.s->o + rb * 4096);
      while (__any_sync(0xffffffffu, (ld_rlx1(osrc + (wq * 8 + (lane & 7)) * 2048 + wq * 512 + 508) ^ par) & 1)) {}
      bar_sync_wg(wg);
      if (wg) bar_sync<7, 256>();
      osrc += wq * 8192;
      const uint32_t od0 = wq < 2 ? me + SM_W + (6 + wg) * 16384 + wq * 8192 : kvb + (wq - 2) * 8192, od1 = kvb + 16384 + wq * 8192;
      if (elect()) { mbar_expect(G.bar, 8192); bulk_g2s(od0, osrc, 8192, G.bar); mbar_expect(G.bar + 8, 8192); bulk_g2s(od1, osrc + 32768, 8192, G.bar + 8); }
      if (!wg) asm volatile("bar.arrive 7, 256;" ::: "memory");
      #pragma unroll
      for (int k = 4; k < 32; k++) ldsm4t(a[k], wa + k * 2048);
      auto check = [&](int h) {
        const uint32_t od = h ? od1 : od0;
        #pragma unroll 1
        while (true) {
          G.wait(h);
          uint32_t x = 0;
          #pragma unroll
          for (int i = 0; i < 16; i++) x = tagacc(x, lds1(od + i * 512 + lane * 16 + (lane >> 3) * 4), par);
          if (!__any_sync(0xffffffffu, x & 1)) break;
          if (elect()) { mbar_expect(G.bar + 8 * h, 8192); bulk_g2s(od, osrc + h * 32768, 8192, G.bar + 8 * h); }
        }
      };
      float acc[32];
      check(0);
      if (wg) check(1);
      turn_begin(wg);
      wg_fence();
      wgmma_n64<0, 0>(acc, a[0], P.dob + wg * 1024);
      #pragma unroll
      for (int k = 1; k < 16; k++) wgmma_n64<0, 1>(acc, a[k], k < 8 ? P.dob + wg * 1024 + k * 128 : P.dob + wg * 3072 + 1024 + k * 128);
      wg_commit();
      if (!wg) { check(1); bar_sync_wg(wg); }
      wg_fence();
      #pragma unroll
      for (int k = 16; k < 32; k++) wgmma_n64<0, 1>(acc, a[k], P.dob + wg * 3072 + 1024 + k * 128);
      wg_commit();
      uint32_t ga[2][4];
      lds4(ga[0], me + SM_GA + t * 32); lds4(ga[1], me + SM_GA + t * 32 + 16);
      wg_wait<1>();
      bar_sync_wg(wg);
      wg_wait<0>(); pin(acc);
      #pragma unroll
      for (int j = 0; j < 4; j++)
        stsm4t(me + SM_W + (6 + wg) * 16384 + j * 4096 + (xo ^ (wq << 5)), pk(acc[8 * j], acc[8 * j + 1]), pk(acc[8 * j + 4], acc[8 * j + 5]), pk(acc[8 * j + 2], acc[8 * j + 3]), pk(acc[8 * j + 6], acc[8 * j + 7]));
      bar_sync_wg(wg);
      #pragma unroll
      for (int k = 0; k < 4; k++) {
        uint32_t y[4]; ldsm4(y, G.buf3 + (xo ^ (k << 5)));
        #pragma unroll
        for (int i = 0; i < 4; i++) xv[k][i] = hfma2(ga[k >> 1][(k & 1) * 2 + (i >> 1)], y[i], xv[k][i]);
        st_tag4(P.s->x1 + (rb * 4 + wq) * 1024 + (4 * r + k) * 32 + lane, xv[k][0], xv[k][1], xv[k][2], xv[k][3], par);
      }
      turn_end(wg);
      sched_fence(me + SM_ROLE + 4);
      float s0 = 0.f, s1 = 0.f, q0 = 0.f, q1 = 0.f;
      #pragma unroll
      for (int j = 0; j < 8; j++) {
        const uint32_t u = xv[j >> 1][(j & 1) * 2], v = xv[j >> 1][(j & 1) * 2 + 1];
        s0 += blo(u) + bhi(u); q0 = fmaf(blo(u), blo(u), fmaf(bhi(u), bhi(u), q0));
        s1 += blo(v) + bhi(v); q1 = fmaf(blo(v), blo(v), fmaf(bhi(v), bhi(v), q1));
      }
      s0 += shx(s0, 1); q0 += shx(q0, 1); s1 += shx(s1, 1); q1 += shx(q1, 1);
      s0 += shx(s0, 2); q0 += shx(q0, 2); s1 += shx(s1, 2); q1 += shx(q1, 2);
      if (t == 0) st_tag4(P.s->stat2 + ((rb * 4 + wq) * 8 + r) * 8 + g, __float_as_uint(s0), __float_as_uint(q0), __float_as_uint(s1), __float_as_uint(q1), par);
    }
    uint32_t gf[28][4];
    {
      G.src = (const uint8_t*)(P.s->x1 + (rb * 4 + wq) * 1024);
      const uint4* sp = P.s->stat2 + (rb * 4 + wq) * 64 + g;
      uint32_t e[8][4];
      while (__any_sync(0xffffffffu, (ld_rlx1(G.src + (wq * 2 + (lane & 1)) * 2048 + 2032) ^ par) & 1)) {}
      bar_sync_wg(wg);
      G.start();
      if (lane < 4) mbar_arrive_cl(((lane & 1) << 24) + B_WEMPTY + 16 + 8 * lane);
      #pragma unroll
      for (int i = 0; i < 8; i++) ld_wk4(e[i], sp + i * 8);
      G.half<0>(&a[0]);
      if (l0) mbar_arrive2_cl(wg * 0x1000008 + B_WEMPTY + 48);
      while (stale<8>(e, par)) {
        #pragma unroll
        for (int i = 0; i < 8; i++) ld_rlx4(e[i], sp + i * 8);
      }
      float z[4];
      #pragma unroll
      for (int i = 0; i < 4; i++)
        z[i] = (((__uint_as_float(e[0][i]) + __uint_as_float(e[1][i])) + (__uint_as_float(e[2][i]) + __uint_as_float(e[3][i])))
              + ((__uint_as_float(e[4][i]) + __uint_as_float(e[5][i])) + (__uint_as_float(e[6][i]) + __uint_as_float(e[7][i])))) * (1.f / 512.f);
      const float m0 = z[0], m1 = z[2], r0 = rsq(fmaxf(z[1] - m0 * m0, 0.f) + 1e-5f), r1 = rsq(fmaxf(z[3] - m1 * m1, 0.f) + 1e-5f);
      const uint32_t rs0 = pk(r0, r0), rs1 = pk(r1, r1), nm0 = pk(-m0 * blo(rs0), -m0 * blo(rs0)), nm1 = pk(-m1 * blo(rs1), -m1 * blo(rs1));
      #pragma unroll
      for (int m = 0; m < 8; m++) modulate(&a[2 * m], &a[2 * m], me + t * 16 + m * 64, rs0, nm0, rs1, nm1);
      G.half<1>(&a[16]);
      #pragma unroll
      for (int m = 8; m < 16; m++) modulate(&a[2 * m], &a[2 * m], me + t * 16 + m * 64, rs0, nm0, rs1, nm1);
      anchor(a, P.never, me + SM_W);
      uint4* gp = P.s->g + ((rb * 8 + r) * 4 + wq) * 448 + lane;
      const uint32_t spill = G.buf + lane * 16;
      G.src = (const uint8_t*)(P.s->g + ((rb * 8 + (r ^ 1)) * 4 + wq) * 448);
      #pragma unroll 1
      for (int ch = 0; ch < 3; ch++) {
        float acc[64]; uint32_t gt[16];
        const Pass W{P.dw128[2], me, (uint32_t)(ch & 1), wg, l0, true};
        turn_begin(wg); gemm_slots<0, 0xCC, 8, 4, 128, 128>(W, acc, a);
        gemm_finish<7>(W, acc);
        glu<16>(acc, gt);
        #pragma unroll
        for (int j = 0; j < 4; j++) {
          st_tag4(gp + (ch * 4 + j) * 32, gt[4 * j], gt[4 * j + 1], gt[4 * j + 2], gt[4 * j + 3], par);
          sts4(spill + ch * 2048 + j * 512, gt[4 * j], gt[4 * j + 1], gt[4 * j + 2], gt[4 * j + 3]);
        }
      }
      #pragma unroll
      for (int j = 0; j < 4; j++) lds4(gf[j], spill + j * 512);
      float acc[32];
      const Pass W{P.dw64, me, 1, wg, l0, true};
      turn_begin(wg); gemm_slots<0, 0xC, 4, 8, 64, 64>(W, acc, a);
      if (elect()) { mbar_expect(G.bar, 6144); bulk_g2s(G.buf + 6144, G.src, 6144, G.bar); }
      gemm_finish<3>(W, acc);
      #pragma unroll
      for (int j = 4; j < 12; j++) lds4(gf[j], spill + j * 512);
      glu<8>(acc, &gf[12][0]);
      #pragma unroll
      for (int j = 12; j < 14; j++) st_tag4(gp + j * 32, gf[j][0], gf[j][1], gf[j][2], gf[j][3], par);
      #pragma unroll
      for (int j = 0; j < 14; j++) pin(gf[j]);
    }
    {
      uint4* base = P.s->part + rb * 12288 + tau;
      {
        float acc[64];
        Pass W{P.dw2, me, 1, wg, l0, true};
        turn_begin(wg); gemm_pairs<4, 0, false>(W, acc, gf);
        #pragma unroll
        for (int j = 26; j < 28; j++) ld_rlx4(gf[j], G.src + (j - 14) * 512 + lane * 16);
        #pragma unroll 1
        while (true) {
          G.wait(0);
          #pragma unroll
          for (int j = 14; j < 26; j++) lds4(gf[j], G.buf + lane * 16 + (j - 2) * 512);
          if (!stale<12>(&gf[14], par)) break;
          if (elect()) { mbar_expect(G.bar, 6144); bulk_g2s(G.buf + 6144, G.src, 6144, G.bar); }
        }
        gemm_finish<6>(W, acc); w_release<7>(W);
        while (stale<2>(&gf[26], par)) {
          #pragma unroll
          for (int j = 26; j < 28; j++) ld_rlx4(gf[j], G.src + (j - 14) * 512 + lane * 16);
        }
        #pragma unroll
        for (int j = 14; j < 28; j++) pin(gf[j]);
        W.ph = 0;
        turn_begin(wg); gemm_pairs<0, 14, true>(W, acc, gf);
        gemm_finish<2>(W, acc); w_release<3>(W);
        uint4* const pp[2] = {fix(base + ((r + 2) & 7) * 1536), fix(base + ((r + 4) & 7) * 1536 + 512)};
        #pragma unroll
        for (int j = 0; j < 8; j++)
          st_tag4(pp[j >> 2] + (j & 3) * 128, pk(acc[8 * j], acc[8 * j + 1]), pk(acc[8 * j + 2], acc[8 * j + 3]), pk(acc[8 * j + 4], acc[8 * j + 5]), pk(acc[8 * j + 6], acc[8 * j + 7]), par);
      }
      float acc[32];
      const uint4* in = base + r * 1536;
      uint32_t pa[12][4], xr[4][4];
      {
        const Pass W{P.dw128[3], me, 0, wg, false, true};
        turn_begin(wg); gemm_slots<4, 0xC, 4, 7, 128, 64, 0>(W, acc, gf);
        gemm_finish<-1>(W, acc);
        #pragma unroll
        for (int j = 0; j < 4; j++)
          st_tag4(base + (((r + 6) & 7) * 3 + 2) * 512 + j * 128, pk(acc[8 * j], acc[8 * j + 1]), pk(acc[8 * j + 2], acc[8 * j + 3]), pk(acc[8 * j + 4], acc[8 * j + 5]), pk(acc[8 * j + 6], acc[8 * j + 7]), par);
      }
      const Pass W{P.dw128[4], me, 1, wg, false, wg == 0};
      #pragma unroll
      for (int j = 0; j < 4; j++) ld_wk4(xr[j], P.s->x1 + (rb * 4 + wq) * 1024 + (4 * r + j) * 32 + lane);
      turn_begin(wg);
      #pragma unroll
      for (int k = 0; k < 8; k++) ld_wk4(pa[k], in + k * 128);
      gemm_slots<0, 0xC, 4, 7, 128, 64, 0>(W, acc, gf);
      #pragma unroll
      for (int k = 8; k < 12; k++) ld_wk4(pa[k], in + k * 128);
      gemm_finish<-1>(W, acc);
      while (__builtin_expect(stale<8>(pa, par), 0)) {
        #pragma unroll
        for (int k = 0; k < 8; k++) ld_rlx4(pa[k], in + k * 128);
      }
      #pragma unroll
      for (int j = 0; j < 16; j++) { acc[2 * j] += blo(pa[j >> 2][j & 3]) + blo(pa[4 + (j >> 2)][j & 3]); acc[2 * j + 1] += bhi(pa[j >> 2][j & 3]) + bhi(pa[4 + (j >> 2)][j & 3]); }
      pin(acc);
      while (__builtin_expect(stale<4>(&pa[8], par), 0)) {
        #pragma unroll
        for (int k = 8; k < 12; k++) ld_rlx4(pa[k], in + k * 128);
      }
      #pragma unroll
      for (int j = 0; j < 16; j++) { acc[2 * j] += blo(pa[8 + (j >> 2)][j & 3]); acc[2 * j + 1] += bhi(pa[8 + (j >> 2)][j & 3]); }
      const uint32_t xo = tile_off();
      uint32_t gb[2][4];
      lds4(gb[0], me + SM_GB + t * 32); lds4(gb[1], me + SM_GB + t * 32 + 16);
      #pragma unroll
      for (int k = 0; k < 4; k++) {
        uint32_t y[4];
        #pragma unroll
        for (int i = 0; i < 4; i++) {
          const uint32_t gw = gb[k >> 1][(k & 1) * 2 + (i >> 1)];
          y[i] = pk(fmaf(blo(gw), acc[8 * k + 2 * i], blo(xr[k][i])), fmaf(bhi(gw), acc[8 * k + 2 * i + 1], bhi(xr[k][i])));
        }
        stsm4(G.buf + (xo ^ (k << 5)), y[0], y[1], y[2], y[3]);
      }
      __syncwarp();
      uint8_t* op = fix(P.out + (xrow + (lane >> 3)) * 1024 + r * 128 + (lane & 7) * 16);
      #pragma unroll
      for (int k = 0; k < 4; k++) {
        uint32_t y[4]; const int row = k * 4 + (lane >> 3);
        lds4(y, G.buf + row * 128 + (((lane ^ row) & 7) << 4));
        asm volatile("st.global.v4.u32 [%0], {%1,%2,%3,%4};" :: "l"(op + k * 4096), "r"(y[0]), "r"(y[1]), "r"(y[2]), "r"(y[3]) : "memory");
      }
    }
    if (l0) mbar_arrive(me + B_DONE);
    __syncwarp();
    cl_arrive_relaxed(); cl_wait();
  }
}

typedef CUresult (*EncodeFn)(CUtensorMap*, CUtensorMapDataType, cuuint32_t, void*, const cuuint64_t*, const cuuint64_t*, const cuuint32_t*, const cuuint32_t*,
                             CUtensorMapInterleave, CUtensorMapSwizzle, CUtensorMapL2promotion, CUtensorMapFloatOOBfill);

void map2d(EncodeFn enc, CUtensorMap* m, void* p, uint64_t ncols, uint64_t nrows, uint32_t bn, uint32_t bk, CUtensorMapSwizzle sw) {
  cuuint64_t dims[2] = {ncols, nrows}, str[1] = {ncols * 2};
  cuuint32_t box[2] = {bn, bk}, es[2] = {1, 1};
  enc(m, CU_TENSOR_MAP_DATA_TYPE_BFLOAT16, 2, p, dims, str, box, es, CU_TENSOR_MAP_INTERLEAVE_NONE, sw, CU_TENSOR_MAP_L2_PROMOTION_L2_128B, CU_TENSOR_MAP_FLOAT_OOB_FILL_NONE);
}
constexpr uint64_t desc(uint32_t addr, uint32_t lbo, uint32_t sbo, uint32_t mode) {
  return (uint64_t)(addr >> 4) + ((uint64_t)(lbo >> 4) << 16) + ((uint64_t)(sbo >> 4) << 32) + ((uint64_t)mode << 62);
}

}

extern "C" void kernel_launch(void* const* d_in, const int* in_sizes, int n_in, void* d_out, int out_size) {
  static EncodeFn enc = nullptr;
  static Scratch* scratch = nullptr;
  if (!enc) {
    cudaDriverEntryPointQueryResult qr;
    cudaGetDriverEntryPoint("cuTensorMapEncodeTiled", (void**)&enc, cudaEnableDefault, &qr);
    cudaGetSymbolAddress((void**)&scratch, g_s);
    cudaFuncSetAttribute(fused_block_kernel, cudaFuncAttributeMaxDynamicSharedMemorySize, SM_ALLOC);
  }
  Params P;
  {
    cuuint64_t dims[3] = {64, 2048, 8}, str[2] = {1024, 128};
    cuuint32_t box[3] = {64, 16, 2}, es[3] = {1, 1, 1};
    enc(&P.tm_x, CU_TENSOR_MAP_DATA_TYPE_BFLOAT16, 3, d_in[0], dims, str, box, es, CU_TENSOR_MAP_INTERLEAVE_NONE, CU_TENSOR_MAP_SWIZZLE_128B,
        CU_TENSOR_MAP_L2_PROMOTION_L2_128B, CU_TENSOR_MAP_FLOAT_OOB_FILL_NONE);
  }
  map2d(enc, &P.tm_qkv, d_in[1], 1536, 512, 64, 64, CU_TENSOR_MAP_SWIZZLE_128B);
  map2d(enc, &P.tm_wo, d_in[2], 512, 512, 64, 128, CU_TENSOR_MAP_SWIZZLE_128B);
  map2d(enc, &P.tm_g64, d_in[4], 1792, 512, 64, 64, CU_TENSOR_MAP_SWIZZLE_128B);
  map2d(enc, &P.tm_u64, d_in[5], 1792, 512, 64, 64, CU_TENSOR_MAP_SWIZZLE_128B);
  map2d(enc, &P.tm_g32, d_in[4], 1792, 512, 32, 128, CU_TENSOR_MAP_SWIZZLE_64B);
  map2d(enc, &P.tm_u32, d_in[5], 1792, 512, 32, 128, CU_TENSOR_MAP_SWIZZLE_64B);
  map2d(enc, &P.tm_wd, d_in[6], 512, 1792, 64, 112, CU_TENSOR_MAP_SWIZZLE_128B);
  P.x = (const uint8_t*)d_in[0]; P.wqkv = (const uint8_t*)d_in[1]; P.c = (const uint8_t*)d_in[7]; P.wmod = (const uint8_t*)d_in[8];
  P.wo = (const uint8_t*)d_in[2]; P.wg = (const uint8_t*)d_in[4]; P.wu = (const uint8_t*)d_in[5]; P.wd = (const uint8_t*)d_in[6];
  P.out = (uint8_t*)d_out; P.s = scratch;
  P.never = 0; P.m1 = 0xFFFFFFFFu;
  for (int k = 0; k < 66; k++)
    P.role[k] = k < 32 ? (k & 7) * 8 + (k >> 3) : k < 60 ? (1 + (k - 32) % 7) * 8 + 4 + (k - 32) / 7 : k < 62 ? k + 4 : k - 58;
  for (int i = 0; i < 5; i++) P.dw128[i] = desc(SM_W, 8192, 1024, 1);
  P.dw64 = desc(SM_W, 8192, 512, 2); P.dw2 = desc(SM_W, 16384, 1024, 1);
  P.dob = desc(SM_W + 6 * 16384, 128, 256, 0); P.dk = desc(SM_G, 2048, 128, 0); P.dv = desc(SM_G + 4096, 128, 2048, 0);
  cudaLaunchConfig_t cfg = {};
  cfg.gridDim = 132; cfg.blockDim = 384; cfg.dynamicSmemBytes = SM_ALLOC; cfg.stream = cudaStreamPerThread;
  cudaLaunchAttribute at[1];
  at[0].id = cudaLaunchAttributeClusterDimension; at[0].val.clusterDim.x = 2; at[0].val.clusterDim.y = 1; at[0].val.clusterDim.z = 1;
  cfg.attrs = at; cfg.numAttrs = 1;
  cudaLaunchKernelEx(&cfg, fused_block_kernel, P);
}
```
